```python
import torch

def _softmax(x, axis=-1):
    return torch.softmax(x, dim=axis)

def _gelu(x):
    return torch.nn.functional.gelu(x, approximate='tanh')

def _silu(x):
    return torch.nn.functional.silu(x)

def _sigmoid(x):
    return torch.sigmoid(x)

def _layernorm(x, axis=-1, eps=1e-05):
    m = x.mean(dim=axis, keepdim=True)
    v = x.var(dim=axis, keepdim=True, unbiased=False)
    return (x - m) / torch.sqrt(v + eps)

def _scatter_add(tgt, idx, src, axis=0):
    return tgt.clone().index_add_(axis, idx, src)

def _segment_sum(src, seg, n):
    out = torch.zeros((n,) + src.shape[1:], dtype=src.dtype)
    return out.index_add_(0, seg, src)

def _pad(x, pw):
    flat = tuple((v for pair in reversed(pw) for v in pair))
    return torch.nn.functional.pad(x, flat)
kernel_name = 'standalone__tree_speculative_verify_tree_attention_over_candidate_token_tree__sampling'

def setup_inputs():

    _w = lambda a: (lambda t: t.to(torch.bfloat16) if t.is_floating_point() else t)(torch.as_tensor(a))
    B, Hq, Hkv, T, C, D = (8, 32, 8, 8, 4096, 128)
    tree_mask = torch.zeros((B, T, T), dtype=float)
    for b in range(B):
        parent = torch.zeros(T, dtype=torch.int64)
        for i in range(1, T):
            parent[i] = int(torch.randint(0, i, (1,)).item())
        for i in range(T):
            j = i
            tree_mask[b, i, j] = 1.0
            while j > 0:
                j = parent[j]
                tree_mask[b, i, j] = 1.0
    return {'q': _w((lambda *s: torch.randn(*s, dtype=torch.bfloat16) * 0.8)(B, Hq, T, D)), 'k_cache': _w((lambda *s: torch.randn(*s, dtype=torch.bfloat16) * 0.8)(B, Hkv, C, D)), 'v_cache': _w((lambda *s: torch.randn(*s, dtype=torch.bfloat16) * 0.05)(B, Hkv, C, D)), 'k_tree': _w((lambda *s: torch.randn(*s, dtype=torch.bfloat16) * 0.8)(B, Hkv, T, D)), 'v_tree': _w((lambda *s: torch.randn(*s, dtype=torch.bfloat16) * 0.05)(B, Hkv, T, D)), 'tree_mask': _w(tree_mask)}

def reference(q, k_cache, v_cache, k_tree, v_tree, tree_mask):
    B, Hq, T, D = q.shape
    Hkv, C = (k_cache.shape[1], k_cache.shape[2])
    rep = Hq // Hkv
    kc = (lambda x, n, axis: torch.repeat_interleave(x, n, dim=axis))(k_cache, rep, axis=1)
    vc = (lambda x, n, axis: torch.repeat_interleave(x, n, dim=axis))(v_cache, rep, axis=1)
    kt = (lambda x, n, axis: torch.repeat_interleave(x, n, dim=axis))(k_tree, rep, axis=1)
    vt = (lambda x, n, axis: torch.repeat_interleave(x, n, dim=axis))(v_tree, rep, axis=1)
    k = torch.concatenate([kc, kt], axis=2)
    v = torch.concatenate([vc, vt], axis=2)
    scale = D ** (-0.5)
    scores = torch.einsum('bhqd,bhkd->bhqk', q, k) * scale
    ctx_mask = torch.ones((B, 1, T, C), dtype=scores.dtype)
    tm = tree_mask[:, None, :, :].clone()
    full_mask = torch.concatenate([ctx_mask, tm], axis=-1)
    scores = scores + (1.0 - full_mask) * -1000000000.0
    p = _softmax(scores, axis=-1)
    return torch.einsum('bhqk,bhkd->bhqd', p, v)
```

```cpp
#include <cuda_runtime.h>
#include <cuda_bf16.h>
#include <cuda.h>
#include <stdint.h>

namespace tsv {

constexpr int kB = 8, kHq = 32, kHkv = 8, kT = 8, kC = 4096, kD = 128;
constexpr int kRep = kHq / kHkv;
constexpr int kRows = kRep * kT;
constexpr int kSplit = 2;
constexpr int kKeysPerCta = kC / kSplit;
#define TSV_TILE 64
#define TSV_SLOTS 12
constexpr int kTile = TSV_TILE;
constexpr int kNT = kKeysPerCta / kTile;
constexpr int kSlots = TSV_SLOTS;
constexpr int kSlotBytes = kTile * kD * 2;
constexpr int kHalfBytes = kTile * 128;
constexpr int kThreads = 160;

constexpr int kOffRing = 0;
constexpr int kOffKTree = kOffRing + kSlots * kSlotBytes;
constexpr int kOffVTree = kOffKTree + 2048;
constexpr int kOffXbuf = kOffVTree + 4096;
constexpr int kXbufBytes = 17 * 32 * 16;
constexpr int kOffBars = kOffXbuf + kXbufBytes;
constexpr int kSmemBytes = kOffBars + (2 * kSlots + 1) * 8 + 1024;

__device__ __forceinline__ uint32_t smem_u32(const void* p) {
    return (uint32_t)__cvta_generic_to_shared(p);
}
__device__ __forceinline__ void mbar_init(uint32_t bar, uint32_t count) {
    asm volatile("mbarrier.init.shared::cta.b64 [%0], %1;" ::"r"(bar), "r"(count) : "memory");
}
__device__ __forceinline__ void mbar_expect_tx(uint32_t bar, uint32_t bytes) {
    asm volatile("mbarrier.arrive.expect_tx.shared::cta.b64 _, [%0], %1;" ::"r"(bar), "r"(bytes) : "memory");
}
__device__ __forceinline__ void mbar_arrive(uint32_t bar) {
    asm volatile("mbarrier.arrive.shared::cta.b64 _, [%0];" ::"r"(bar) : "memory");
}
__device__ __forceinline__ bool mbar_try_wait(uint32_t bar, uint32_t parity) {
    uint32_t ok;
    asm volatile(
        "{\n.reg .pred p;\n"
        "mbarrier.try_wait.parity.shared::cta.b64 p, [%1], %2;\n"
        "selp.u32 %0, 1, 0, p;\n}\n"
        : "=r"(ok) : "r"(bar), "r"(parity) : "memory");
    return ok != 0;
}
__device__ __forceinline__ void mbar_wait(uint32_t bar, uint32_t parity) {
    uint32_t spins = 0;
    while (!mbar_try_wait(bar, parity)) {
        if (++spins > (1u << 24)) __trap();
    }
}
__device__ __forceinline__ bool mbar_try_wait_cluster(uint32_t bar, uint32_t parity) {
    uint32_t ok;
    asm volatile(
        "{\n.reg .pred p;\n"
        "mbarrier.try_wait.parity.acquire.cluster.shared::cta.b64 p, [%1], %2;\n"
        "selp.u32 %0, 1, 0, p;\n}\n"
        : "=r"(ok) : "r"(bar), "r"(parity) : "memory");
    return ok != 0;
}
__device__ __forceinline__ void mbar_wait_cluster(uint32_t bar, uint32_t parity) {
    uint32_t spins = 0;
    while (!mbar_try_wait_cluster(bar, parity)) {
        if (++spins > (1u << 24)) __trap();
    }
}
__device__ __forceinline__ void tma_load_3d(uint32_t dst, const CUtensorMap* map, uint32_t bar,
                                            int c0, int c1, int c2) {
    asm volatile(
        "cp.async.bulk.tensor.3d.shared::cluster.global.mbarrier::complete_tx::bytes "
        "[%0], [%1, {%3, %4, %5}], [%2];"
        ::"r"(dst), "l"(reinterpret_cast<uint64_t>(map)), "r"(bar), "r"(c0), "r"(c1), "r"(c2)
        : "memory");
}
__device__ __forceinline__ void wgmma_fence() { asm volatile("wgmma.fence.sync.aligned;" ::: "memory"); }
__device__ __forceinline__ void wgmma_commit() { asm volatile("wgmma.commit_group.sync.aligned;" ::: "memory"); }
template <int N>
__device__ __forceinline__ void wgmma_wait() {
    asm volatile("wgmma.wait_group.sync.aligned %0;" ::"n"(N) : "memory");
}
__device__ __forceinline__ uint64_t make_desc(uint32_t addr, uint32_t lbo_bytes, uint32_t sbo_bytes) {
    return (uint64_t)((addr & 0x3FFFF) >> 4) | ((uint64_t)(lbo_bytes >> 4) << 16) |
           ((uint64_t)(sbo_bytes >> 4) << 32) | (1ull << 62);
}
__device__ __forceinline__ float ex2(float x) {
    float y;
    asm("ex2.approx.ftz.f32 %0, %1;" : "=f"(y) : "f"(x));
    return y;
}
__device__ __forceinline__ uint32_t pack_bf16(float lo, float hi) {
    uint32_t r;
    asm("cvt.rn.bf16x2.f32 %0, %1, %2;" : "=r"(r) : "f"(hi), "f"(lo));
    return r;
}

__device__ __forceinline__ void wgmma_n8(float (&d)[4], const uint32_t (&a)[4], uint64_t desc, int scale_d) {
    asm volatile(
        "{\n.reg .pred p;\nsetp.ne.b32 p, %9, 0;\n"
        "wgmma.mma_async.sync.aligned.m64n8k16.f32.bf16.bf16 "
        "{%0,%1,%2,%3}, {%4,%5,%6,%7}, %8, p, 1, 1, 0;\n}\n"
        : "+f"(d[0]), "+f"(d[1]), "+f"(d[2]), "+f"(d[3])
        : "r"(a[0]), "r"(a[1]), "r"(a[2]), "r"(a[3]), "l"(desc), "r"(scale_d));
}

#define TSV_F8(d, o) "+f"(d[o + 0]), "+f"(d[o + 1]), "+f"(d[o + 2]), "+f"(d[o + 3]), \
                     "+f"(d[o + 4]), "+f"(d[o + 5]), "+f"(d[o + 6]), "+f"(d[o + 7])

__device__ __forceinline__ void wgmma_n64(float (&d)[32], const uint32_t (&a)[4], uint64_t desc, int scale_d) {
    asm volatile(
        "{\n.reg .pred p;\nsetp.ne.b32 p, %37, 0;\n"
        "wgmma.mma_async.sync.aligned.m64n64k16.f32.bf16.bf16 "
        "{%0,%1,%2,%3,%4,%5,%6,%7,%8,%9,%10,%11,%12,%13,%14,%15,"
        "%16,%17,%18,%19,%20,%21,%22,%23,%24,%25,%26,%27,%28,%29,%30,%31}, "
        "{%32,%33,%34,%35}, %36, p, 1, 1, 0;\n}\n"
        : TSV_F8(d, 0), TSV_F8(d, 8), TSV_F8(d, 16), TSV_F8(d, 24)
        : "r"(a[0]), "r"(a[1]), "r"(a[2]), "r"(a[3]), "l"(desc), "r"(scale_d));
}

template <int TB>
__device__ __forceinline__ void wgmma_n128(float (&d)[64], const uint32_t (&a)[4], uint64_t desc, int scale_d) {
    asm volatile(
        "{\n.reg .pred p;\nsetp.ne.b32 p, %69, 0;\n"
        "wgmma.mma_async.sync.aligned.m64n128k16.f32.bf16.bf16 "
        "{%0,%1,%2,%3,%4,%5,%6,%7,%8,%9,%10,%11,%12,%13,%14,%15,"
        "%16,%17,%18,%19,%20,%21,%22,%23,%24,%25,%26,%27,%28,%29,%30,%31,"
        "%32,%33,%34,%35,%36,%37,%38,%39,%40,%41,%42,%43,%44,%45,%46,%47,"
        "%48,%49,%50,%51,%52,%53,%54,%55,%56,%57,%58,%59,%60,%61,%62,%63}, "
        "{%64,%65,%66,%67}, %68, p, 1, 1, %70;\n}\n"
        : TSV_F8(d, 0), TSV_F8(d, 8), TSV_F8(d, 16), TSV_F8(d, 24),
          TSV_F8(d, 32), TSV_F8(d, 40), TSV_F8(d, 48), TSV_F8(d, 56)
        : "r"(a[0]), "r"(a[1]), "r"(a[2]), "r"(a[3]), "l"(desc), "r"(scale_d), "n"(TB));
}

template <int NS>
__device__ __forceinline__ void wgmma_s(float (&d)[NS], const uint32_t (&a)[4], uint64_t desc, int scale_d);
template <>
__device__ __forceinline__ void wgmma_s<32>(float (&d)[32], const uint32_t (&a)[4], uint64_t desc, int scale_d) {
    wgmma_n64(d, a, desc, scale_d);
}
template <>
__device__ __forceinline__ void wgmma_s<64>(float (&d)[64], const uint32_t (&a)[4], uint64_t desc, int scale_d) {
    wgmma_n128<0>(d, a, desc, scale_d);
}

__global__ void __cluster_dims__(kSplit, 1, 1) __launch_bounds__(kThreads, 1)
tree_attn_kernel(const __grid_constant__ CUtensorMap map_k,
                 const __grid_constant__ CUtensorMap map_v,
                 const __nv_bfloat16* __restrict__ q,
                 const __nv_bfloat16* __restrict__ k_tree,
                 const __nv_bfloat16* __restrict__ v_tree,
                 const __nv_bfloat16* __restrict__ tree_mask,
                 __nv_bfloat16* __restrict__ out) {
    extern __shared__ uint8_t smem_raw[];
    const uint32_t sbase = (smem_u32(smem_raw) + 1023u) & ~1023u;
    const uint32_t bar_full = sbase + kOffBars;
    const uint32_t bar_empty = bar_full + kSlots * 8;
    const uint32_t bar_x = bar_empty + kSlots * 8;

    const int tid = threadIdx.x;
    const int warp = tid >> 5;
    const int lane = tid & 31;
    const int group = blockIdx.x >> 1;
    const int rank = blockIdx.x & 1;

    if (tid == 0) {
#pragma unroll 1
        for (int i = 0; i < kSlots; i++) {
            mbar_init(bar_full + i * 8, 1);
            mbar_init(bar_empty + i * 8, 4);
        }
        mbar_init(bar_x, 1);
        asm volatile("fence.mbarrier_init.release.cluster;" ::: "memory");
        asm volatile("fence.proxy.async.shared::cta;" ::: "memory");
        mbar_expect_tx(bar_x, kXbufBytes);
    }
    __syncthreads();
    asm volatile("barrier.cluster.arrive.release.aligned;" ::: "memory");

    if (warp == 4) {
        if (lane == 0) {
            const int row0 = group * kC + rank * kKeysPerCta;
            int slot = 0;
            uint32_t phase = 1;
#pragma unroll 1
            for (int i = 0; i < 2 * kNT; i++) {
                mbar_wait(bar_empty + slot * 8, phase);
                mbar_expect_tx(bar_full + slot * 8, kSlotBytes);
                tma_load_3d(sbase + kOffRing + slot * kSlotBytes, (i & 1) ? &map_v : &map_k,
                            bar_full + slot * 8, 0, row0 + (i >> 1) * kTile, 0);
                if (++slot == kSlots) { slot = 0; phase ^= 1; }
            }
        }
        __syncwarp();
        asm volatile("barrier.cluster.wait.acquire.aligned;" ::: "memory");
    } else {
        const int g = lane >> 2, j = lane & 3;
        const float kScale = 0.08838834764831845f;
        const float c = kScale * 1.4426950408889634f;

        uint32_t qf[8][4];
        if (warp < 2) {
            const uint32_t* q32 = reinterpret_cast<const uint32_t*>(q + (size_t)group * kRows * kD);
            const uint32_t* r0 = q32 + (warp * 16 + g) * (kD / 2) + j;
            const uint32_t* r1 = r0 + 8 * (kD / 2);
#pragma unroll
            for (int kk = 0; kk < 8; kk++) {
                qf[kk][0] = __ldg(r0 + kk * 8);
                qf[kk][1] = __ldg(r1 + kk * 8);
                qf[kk][2] = __ldg(r0 + kk * 8 + 4);
                qf[kk][3] = __ldg(r1 + kk * 8 + 4);
            }
        } else {
#pragma unroll
            for (int kk = 0; kk < 8; kk++) { qf[kk][0] = qf[kk][1] = qf[kk][2] = qf[kk][3] = 0u; }
        }

        float o[64];
#pragma unroll
        for (int i = 0; i < 64; i++) o[i] = 0.f;
        float m0 = -INFINITY, m1 = -INFINITY, l0 = 0.f, l1 = 0.f;

        if (rank == 0) {
            const int r = tid >> 4, ch = tid & 15;
            const uint4 kv = __ldg(reinterpret_cast<const uint4*>(k_tree + (size_t)group * kT * kD) + tid);
            const uint4 vv = __ldg(reinterpret_cast<const uint4*>(v_tree + (size_t)group * kT * kD) + tid);
            const int b = group / kHkv;
            const float mk0 = __bfloat162float(tree_mask[b * kT * kT + g * kT + 2 * j]);
            const float mk1 = __bfloat162float(tree_mask[b * kT * kT + g * kT + 2 * j + 1]);
            const uint32_t sw = (uint32_t)(((ch & 7) ^ r) * 16 + r * 128);
            const uint32_t ka = sbase + kOffKTree + (ch >> 3) * 1024 + sw;
            const uint32_t va = sbase + kOffVTree + (ch >> 3) * 2048 + sw;
            asm volatile("st.shared.v4.b32 [%0], {%1,%2,%3,%4};" ::"r"(ka), "r"(kv.x), "r"(kv.y), "r"(kv.z), "r"(kv.w) : "memory");
            asm volatile("st.shared.v4.b32 [%0], {%1,%2,%3,%4};" ::"r"(va), "r"(vv.x), "r"(vv.y), "r"(vv.z), "r"(vv.w) : "memory");
            asm volatile("st.shared.v4.b32 [%0], {%1,%1,%1,%1};" ::"r"(va + 1024), "r"(0u) : "memory");
            asm volatile("fence.proxy.async.shared::cta;" ::: "memory");
            asm volatile("bar.sync 1, 128;" ::: "memory");

            float s[4];
            wgmma_fence();
#pragma unroll
            for (int kk = 0; kk < 8; kk++) {
                wgmma_n8(s, qf[kk], make_desc(sbase + kOffKTree + (kk >> 2) * 1024 + (kk & 3) * 32, 16, 1024), kk);
            }
            wgmma_commit();
            wgmma_wait<0>();
            const float madd = -1.0e9f / kScale;
            s[0] += (1.f - mk0) * madd; s[1] += (1.f - mk1) * madd;
            s[2] += (1.f - mk0) * madd; s[3] += (1.f - mk1) * madd;
            float mx0 = fmaxf(s[0], s[1]), mx1 = fmaxf(s[2], s[3]);
            mx0 = fmaxf(mx0, __shfl_xor_sync(0xffffffffu, mx0, 1));
            mx1 = fmaxf(mx1, __shfl_xor_sync(0xffffffffu, mx1, 1));
            mx0 = fmaxf(mx0, __shfl_xor_sync(0xffffffffu, mx0, 2));
            mx1 = fmaxf(mx1, __shfl_xor_sync(0xffffffffu, mx1, 2));
            m0 = mx0; m1 = mx1;
            const float p0 = ex2((s[0] - m0) * c), p1 = ex2((s[1] - m0) * c);
            const float p2 = ex2((s[2] - m1) * c), p3 = ex2((s[3] - m1) * c);
            l0 = p0 + p1; l1 = p2 + p3;
            uint32_t pa[4] = {pack_bf16(p0, p1), pack_bf16(p2, p3), 0u, 0u};
            wgmma_fence();
            wgmma_n128<1>(o, pa, make_desc(sbase + kOffVTree, 2048, 1024), 1);
            wgmma_commit();
            wgmma_wait<0>();
        }

        int slot = 0;
        uint32_t phase = 0;
#pragma unroll 1
        for (int it = 0; it < kNT; it++) {
            float s[kTile / 2];
            {
                const uint32_t kb = sbase + kOffRing + slot * kSlotBytes;
                mbar_wait(bar_full + slot * 8, phase);
                wgmma_fence();
#pragma unroll
                for (int kk = 0; kk < 8; kk++) {
                    wgmma_s<kTile / 2>(s, qf[kk], make_desc(kb + (kk >> 2) * kHalfBytes + (kk & 3) * 32, 16, 1024), kk);
                }
                wgmma_commit();
                wgmma_wait<0>();
                if (lane == 0) mbar_arrive(bar_empty + slot * 8);
                if (++slot == kSlots) { slot = 0; phase ^= 1; }
            }
            float mx0 = s[0], mx1 = s[2];
#pragma unroll
            for (int i = 0; i < kTile / 8; i++) {
                mx0 = fmaxf(mx0, fmaxf(s[4 * i], s[4 * i + 1]));
                mx1 = fmaxf(mx1, fmaxf(s[4 * i + 2], s[4 * i + 3]));
            }
            mx0 = fmaxf(mx0, __shfl_xor_sync(0xffffffffu, mx0, 1));
            mx1 = fmaxf(mx1, __shfl_xor_sync(0xffffffffu, mx1, 1));
            mx0 = fmaxf(mx0, __shfl_xor_sync(0xffffffffu, mx0, 2));
            mx1 = fmaxf(mx1, __shfl_xor_sync(0xffffffffu, mx1, 2));
            const float mn0 = fmaxf(m0, mx0), mn1 = fmaxf(m1, mx1);
            const float a0 = ex2((m0 - mn0) * c), a1 = ex2((m1 - mn1) * c);
            m0 = mn0; m1 = mn1;
            const float mc0 = mn0 * c, mc1 = mn1 * c;
            float rs0 = 0.f, rs1 = 0.f;
            uint32_t pf[kTile / 16][4];
#pragma unroll
            for (int i = 0; i < kTile / 8; i++) {
                const float p0 = ex2(fmaf(s[4 * i], c, -mc0));
                const float p1 = ex2(fmaf(s[4 * i + 1], c, -mc0));
                const float p2 = ex2(fmaf(s[4 * i + 2], c, -mc1));
                const float p3 = ex2(fmaf(s[4 * i + 3], c, -mc1));
                rs0 += p0 + p1;
                rs1 += p2 + p3;
                pf[i >> 1][(i & 1) * 2] = pack_bf16(p0, p1);
                pf[i >> 1][(i & 1) * 2 + 1] = pack_bf16(p2, p3);
            }
            l0 = l0 * a0 + rs0;
            l1 = l1 * a1 + rs1;
#pragma unroll
            for (int i = 0; i < 16; i++) {
                o[4 * i] *= a0; o[4 * i + 1] *= a0;
                o[4 * i + 2] *= a1; o[4 * i + 3] *= a1;
            }
            {
                const uint32_t vb = sbase + kOffRing + slot * kSlotBytes;
                mbar_wait(bar_full + slot * 8, phase);
                wgmma_fence();
#pragma unroll
                for (int kk = 0; kk < kTile / 16; kk++) {
                    wgmma_n128<1>(o, pf[kk], make_desc(vb + kk * 2048, kHalfBytes, 1024), 1);
                }
                wgmma_commit();
                wgmma_wait<0>();
                if (lane == 0) mbar_arrive(bar_empty + slot * 8);
                if (++slot == kSlots) { slot = 0; phase ^= 1; }
            }
        }

        l0 += __shfl_xor_sync(0xffffffffu, l0, 1);
        l1 += __shfl_xor_sync(0xffffffffu, l1, 1);
        l0 += __shfl_xor_sync(0xffffffffu, l0, 2);
        l1 += __shfl_xor_sync(0xffffffffu, l1, 2);

        asm volatile("barrier.cluster.wait.acquire.aligned;" ::: "memory");

        if (warp == (rank ^ 1)) {
            uint32_t rbuf, rbar;
            const uint32_t lbuf = sbase + kOffXbuf + lane * 16;
            asm volatile("mapa.shared::cluster.u32 %0, %1, %2;" : "=r"(rbuf) : "r"(lbuf), "r"(rank ^ 1));
            asm volatile("mapa.shared::cluster.u32 %0, %1, %2;" : "=r"(rbar) : "r"(bar_x), "r"(rank ^ 1));
#pragma unroll
            for (int i = 0; i < 16; i++) {
                asm volatile(
                    "st.async.weak.shared::cluster.mbarrier::complete_tx::bytes.v4.f32 [%0], {%1,%2,%3,%4}, [%5];"
                    ::"r"(rbuf + i * 512), "f"(o[4 * i]), "f"(o[4 * i + 1]), "f"(o[4 * i + 2]), "f"(o[4 * i + 3]), "r"(rbar)
                    : "memory");
            }
            asm volatile(
                "st.async.weak.shared::cluster.mbarrier::complete_tx::bytes.v4.f32 [%0], {%1,%2,%3,%4}, [%5];"
                ::"r"(rbuf + 16 * 512), "f"(m0), "f"(m1), "f"(l0), "f"(l1), "r"(rbar)
                : "memory");
        } else if (warp == rank) {
            mbar_wait_cluster(bar_x, 0);
            const uint32_t lbuf = sbase + kOffXbuf + lane * 16;
            float pm0, pm1, pl0, pl1;
            asm volatile("ld.shared.v4.f32 {%0,%1,%2,%3}, [%4];" : "=f"(pm0), "=f"(pm1), "=f"(pl0), "=f"(pl1) : "r"(lbuf + 16 * 512) : "memory");
            const float mn0 = fmaxf(m0, pm0), mn1 = fmaxf(m1, pm1);
            float wa0 = ex2((m0 - mn0) * c), wb0 = ex2((pm0 - mn0) * c);
            float wa1 = ex2((m1 - mn1) * c), wb1 = ex2((pm1 - mn1) * c);
            const float inv0 = 1.f / (l0 * wa0 + pl0 * wb0);
            const float inv1 = 1.f / (l1 * wa1 + pl1 * wb1);
            wa0 *= inv0; wb0 *= inv0; wa1 *= inv1; wb1 *= inv1;
            uint32_t* o32 = reinterpret_cast<uint32_t*>(out + (size_t)group * kRows * kD);
            uint32_t* w0 = o32 + (warp * 16 + g) * (kD / 2) + j;
            uint32_t* w1 = w0 + 8 * (kD / 2);
#pragma unroll
            for (int i = 0; i < 16; i++) {
                float x0, x1, x2, x3;
                asm volatile("ld.shared.v4.f32 {%0,%1,%2,%3}, [%4];" : "=f"(x0), "=f"(x1), "=f"(x2), "=f"(x3) : "r"(lbuf + i * 512) : "memory");
                w0[i * 4] = pack_bf16(o[4 * i] * wa0 + x0 * wb0, o[4 * i + 1] * wa0 + x1 * wb0);
                w1[i * 4] = pack_bf16(o[4 * i + 2] * wa1 + x2 * wb1, o[4 * i + 3] * wa1 + x3 * wb1);
            }
        }
    }
}

typedef CUresult (*EncodeTiledFn)(CUtensorMap*, CUtensorMapDataType, cuuint32_t, void*, const cuuint64_t*,
                                  const cuuint64_t*, const cuuint32_t*, const cuuint32_t*,
                                  CUtensorMapInterleave, CUtensorMapSwizzle, CUtensorMapL2promotion,
                                  CUtensorMapFloatOOBfill);

static EncodeTiledFn get_encode_fn() {
    static EncodeTiledFn fn = nullptr;
    if (!fn) {
        void* p = nullptr;
        cudaDriverEntryPointQueryResult st;
        cudaGetDriverEntryPoint("cuTensorMapEncodeTiled", &p, cudaEnableDefault, &st);
        fn = reinterpret_cast<EncodeTiledFn>(p);
    }
    return fn;
}

#define TSV_L2PROMO CU_TENSOR_MAP_L2_PROMOTION_L2_256B

static void make_map(CUtensorMap* map, const void* ptr) {
    cuuint64_t gdim[3] = {64, (cuuint64_t)kB * kHkv * kC, 2};
    cuuint64_t gstride[2] = {256, 128};
    cuuint32_t box[3] = {64, (cuuint32_t)kTile, 2};
    cuuint32_t estr[3] = {1, 1, 1};
    get_encode_fn()(map, CU_TENSOR_MAP_DATA_TYPE_BFLOAT16, 3, const_cast<void*>(ptr), gdim, gstride, box, estr,
                    CU_TENSOR_MAP_INTERLEAVE_NONE, CU_TENSOR_MAP_SWIZZLE_128B, TSV_L2PROMO,
                    CU_TENSOR_MAP_FLOAT_OOB_FILL_NONE);
}

}

extern "C" void kernel_launch(void* const* d_in, const int* in_sizes, int n_in,
                              void* d_out, int out_size) {
    using namespace tsv;
    const __nv_bfloat16* q = (const __nv_bfloat16*)d_in[0];
    const __nv_bfloat16* k_cache = (const __nv_bfloat16*)d_in[1];
    const __nv_bfloat16* v_cache = (const __nv_bfloat16*)d_in[2];
    const __nv_bfloat16* k_tree = (const __nv_bfloat16*)d_in[3];
    const __nv_bfloat16* v_tree = (const __nv_bfloat16*)d_in[4];
    const __nv_bfloat16* tree_mask = (const __nv_bfloat16*)d_in[5];
    __nv_bfloat16* out = (__nv_bfloat16*)d_out;

    CUtensorMap map_k, map_v;
    make_map(&map_k, k_cache);
    make_map(&map_v, v_cache);

    static bool attr_set = false;
    if (!attr_set) {
        cudaFuncSetAttribute(tree_attn_kernel, cudaFuncAttributeMaxDynamicSharedMemorySize, kSmemBytes);
        attr_set = true;
    }
    tree_attn_kernel<<<kB * kHkv * kSplit, kThreads, kSmemBytes>>>(map_k, map_v, q, k_tree, v_tree, tree_mask, out);
}
```

```cpp
#include <cuda_runtime.h>
#include <cuda_bf16.h>
#include <cuda.h>
#include <stdint.h>

namespace tsv {

#define TRACE(i) do { } while (0)
#define TRACE2(i) do { } while (0)

constexpr int kB = 8, kHq = 32, kHkv = 8, kT = 8, kC = 4096, kD = 128;
constexpr int kRep = kHq / kHkv;
constexpr int kRows = kRep * kT;
constexpr int kSplit = 2;
constexpr int kKeysPerCta = kC / kSplit;
#define TSV_SLOTS 8
#define TSV_INFLIGHT 4
constexpr int kTile = 64;
constexpr int kNT = kKeysPerCta / kTile;
constexpr int kSlots = TSV_SLOTS;
constexpr int kInflight = TSV_INFLIGHT;
static_assert(kSlots % 4 == 0, "each ring slot must always belong to the same consumer warpgroup");
constexpr int kSlotBytes = kTile * kD * 2;
constexpr int kThreads = 288;

constexpr int kOffRing = 0;
constexpr int kOffKTree = kOffRing + kSlots * kSlotBytes;
constexpr int kOffVTree = kOffKTree + 2048;
constexpr int kOffXbuf = kOffVTree + 2048;
constexpr int kXPart = 9 * 32 * 16;
constexpr int kXbufBytes = 2 * 3 * kXPart;
constexpr int kOffBars = kOffXbuf + kXbufBytes;
constexpr int kSmemBytes = kOffBars + (2 * kSlots + 2) * 8 + 1024;

__device__ __forceinline__ uint32_t smem_u32(const void* p) {
    return (uint32_t)__cvta_generic_to_shared(p);
}
__device__ __forceinline__ void mbar_init(uint32_t bar, uint32_t count) {
    asm volatile("mbarrier.init.shared::cta.b64 [%0], %1;" ::"r"(bar), "r"(count) : "memory");
}
__device__ __forceinline__ void mbar_expect_tx(uint32_t bar, uint32_t bytes) {
    asm volatile("mbarrier.arrive.expect_tx.shared::cta.b64 _, [%0], %1;" ::"r"(bar), "r"(bytes) : "memory");
}
__device__ __forceinline__ void mbar_arrive(uint32_t bar) {
    asm volatile("mbarrier.arrive.shared::cta.b64 _, [%0];" ::"r"(bar) : "memory");
}
__device__ __forceinline__ bool mbar_try_wait(uint32_t bar, uint32_t parity) {
    uint32_t ok;
    asm volatile(
        "{\n.reg .pred p;\n"
        "mbarrier.try_wait.parity.shared::cta.b64 p, [%1], %2;\n"
        "selp.u32 %0, 1, 0, p;\n}\n"
        : "=r"(ok) : "r"(bar), "r"(parity) : "memory");
    return ok != 0;
}
__device__ __forceinline__ void mbar_wait(uint32_t bar, uint32_t parity) {
    uint32_t spins = 0;
    while (!mbar_try_wait(bar, parity)) {
        if (++spins > (1u << 20)) __trap();
    }
}
__device__ __forceinline__ bool mbar_try_wait_cluster(uint32_t bar, uint32_t parity) {
    uint32_t ok;
    asm volatile(
        "{\n.reg .pred p;\n"
        "mbarrier.try_wait.parity.acquire.cluster.shared::cta.b64 p, [%1], %2;\n"
        "selp.u32 %0, 1, 0, p;\n}\n"
        : "=r"(ok) : "r"(bar), "r"(parity) : "memory");
    return ok != 0;
}
__device__ __forceinline__ void mbar_wait_cluster(uint32_t bar, uint32_t parity) {
    uint32_t spins = 0;
    while (!mbar_try_wait_cluster(bar, parity)) {
        if (++spins > (1u << 20)) __trap();
    }
}
__device__ __forceinline__ void tma_load_2d(uint32_t dst, const CUtensorMap* map, uint32_t bar,
                                            int c0, int c1) {
    asm volatile(
        "cp.async.bulk.tensor.2d.shared::cluster.global.mbarrier::complete_tx::bytes "
        "[%0], [%1, {%3, %4}], [%2];"
        ::"r"(dst), "l"(reinterpret_cast<uint64_t>(map)), "r"(bar), "r"(c0), "r"(c1)
        : "memory");
}
__device__ __forceinline__ void wgmma_fence() { asm volatile("wgmma.fence.sync.aligned;" ::: "memory"); }
__device__ __forceinline__ void wgmma_commit() { asm volatile("wgmma.commit_group.sync.aligned;" ::: "memory"); }
template <int N>
__device__ __forceinline__ void wgmma_wait() {
    asm volatile("wgmma.wait_group.sync.aligned %0;" ::"n"(N) : "memory");
}
__device__ __forceinline__ uint64_t make_desc(uint32_t addr) {
    return (uint64_t)((addr & 0x3FFFF) >> 4) | (1ull << 16) | (64ull << 32) | (1ull << 62);
}
__device__ __forceinline__ float ex2(float x) {
    float y;
    asm("ex2.approx.ftz.f32 %0, %1;" : "=f"(y) : "f"(x));
    return y;
}
__device__ __forceinline__ uint32_t pack_bf16(float lo, float hi) {
    uint32_t r;
    asm("cvt.rn.bf16x2.f32 %0, %1, %2;" : "=r"(r) : "f"(hi), "f"(lo));
    return r;
}

#define TSV_F8(d, o) "+f"(d[o + 0]), "+f"(d[o + 1]), "+f"(d[o + 2]), "+f"(d[o + 3]), \
                     "+f"(d[o + 4]), "+f"(d[o + 5]), "+f"(d[o + 6]), "+f"(d[o + 7])

__device__ __forceinline__ void wgmma_n16(float (&d)[8], const uint32_t (&a)[4], uint64_t desc, int scale_d) {
    asm volatile(
        "{\n.reg .pred p;\nsetp.ne.b32 p, %13, 0;\n"
        "wgmma.mma_async.sync.aligned.m64n16k16.f32.bf16.bf16 "
        "{%0,%1,%2,%3,%4,%5,%6,%7}, {%8,%9,%10,%11}, %12, p, 1, 1, 0;\n}\n"
        : TSV_F8(d, 0)
        : "r"(a[0]), "r"(a[1]), "r"(a[2]), "r"(a[3]), "l"(desc), "r"(scale_d));
}

__device__ __forceinline__ void wgmma_pv(float (&d)[32], uint32_t a0, uint32_t a1, uint32_t a2, uint32_t a3,
                                         uint64_t desc) {
    asm volatile(
        "wgmma.mma_async.sync.aligned.m64n64k16.f32.bf16.bf16 "
        "{%0,%1,%2,%3,%4,%5,%6,%7,%8,%9,%10,%11,%12,%13,%14,%15,"
        "%16,%17,%18,%19,%20,%21,%22,%23,%24,%25,%26,%27,%28,%29,%30,%31}, "
        "{%32,%33,%34,%35}, %36, 1, 1, 1, 1;\n"
        : TSV_F8(d, 0), TSV_F8(d, 8), TSV_F8(d, 16), TSV_F8(d, 24)
        : "r"(a0), "r"(a1), "r"(a2), "r"(a3), "l"(desc));
}

__device__ __forceinline__ void wgmma_qk(float (&d)[64], const uint32_t (&a)[4], uint64_t desc, int scale_d) {
    asm volatile(
        "{\n.reg .pred p;\nsetp.ne.b32 p, %69, 0;\n"
        "wgmma.mma_async.sync.aligned.m64n128k16.f32.bf16.bf16 "
        "{%0,%1,%2,%3,%4,%5,%6,%7,%8,%9,%10,%11,%12,%13,%14,%15,"
        "%16,%17,%18,%19,%20,%21,%22,%23,%24,%25,%26,%27,%28,%29,%30,%31,"
        "%32,%33,%34,%35,%36,%37,%38,%39,%40,%41,%42,%43,%44,%45,%46,%47,"
        "%48,%49,%50,%51,%52,%53,%54,%55,%56,%57,%58,%59,%60,%61,%62,%63}, "
        "{%64,%65,%66,%67}, %68, p, 1, 1, 0;\n}\n"
        : TSV_F8(d, 0), TSV_F8(d, 8), TSV_F8(d, 16), TSV_F8(d, 24),
          TSV_F8(d, 32), TSV_F8(d, 40), TSV_F8(d, 48), TSV_F8(d, 56)
        : "r"(a[0]), "r"(a[1]), "r"(a[2]), "r"(a[3]), "l"(desc), "r"(scale_d));
}

__global__ void __cluster_dims__(kSplit, 1, 1) __launch_bounds__(kThreads, 1)
tree_attn_kernel(const __grid_constant__ CUtensorMap map_k,
                 const __grid_constant__ CUtensorMap map_v,
                 const __nv_bfloat16* __restrict__ q,
                 const __nv_bfloat16* __restrict__ k_tree,
                 const __nv_bfloat16* __restrict__ v_tree,
                 const __nv_bfloat16* __restrict__ tree_mask,
                 __nv_bfloat16* __restrict__ out) {
    extern __shared__ uint8_t smem_raw[];
    const uint32_t sbase = (smem_u32(smem_raw) + 1023u) & ~1023u;
    const uint32_t bar_full = sbase + kOffBars;
    const uint32_t bar_empty = bar_full + kSlots * 8;
    const uint32_t bar_x = bar_empty + kSlots * 8;

    const int tid = threadIdx.x;
    const int warp = tid >> 5;
    const int lane = tid & 31;
    const int group = blockIdx.x >> 1;
    const int rank = blockIdx.x & 1;
    const int line0 = 2 * (group * kC + rank * kKeysPerCta);

    if (warp == 0) TRACE(0);
    if (tid == 256) {
        TRACE2(0);
        asm volatile("prefetch.tensormap [%0];" ::"l"(reinterpret_cast<uint64_t>(&map_k)) : "memory");
        asm volatile("prefetch.tensormap [%0];" ::"l"(reinterpret_cast<uint64_t>(&map_v)) : "memory");
#pragma unroll
        for (int i = 0; i < kInflight; i++) mbar_init(bar_full + i * 8, 1);
#pragma unroll 1
        for (int i = 0; i < kInflight; i++) {
            if (i == 0) TRACE2(1);
            if (i == 1) TRACE2(2);
            if (i == 2) TRACE2(3);
            mbar_expect_tx(bar_full + i * 8, kSlotBytes);
            tma_load_2d(sbase + kOffRing + i * kSlotBytes, (i & 1) ? &map_v : &map_k,
                        bar_full + i * 8, 0, line0 + (i >> 1) * (2 * kTile));
        }
#pragma unroll 1
        for (int i = 0; i < kSlots; i++) {
            if (i >= kInflight) mbar_init(bar_full + i * 8, 1);
            mbar_init(bar_empty + i * 8, 4);
        }
        mbar_init(bar_x, 1);
        mbar_init(bar_x + 8, 1);
        asm volatile("fence.mbarrier_init.release.cluster;" ::: "memory");
        mbar_expect_tx(bar_x, 3 * kXPart);
        mbar_expect_tx(bar_x + 8, 3 * kXPart);
    }
    if (warp == 8) {
        __syncwarp();
        asm volatile("bar.arrive 2, 288;" ::: "memory");
        asm volatile("barrier.cluster.arrive.relaxed.aligned;" ::: "memory");
        if (lane == 0) {
            int slot = kInflight % kSlots, oslot = 0;
            uint32_t phase = (kInflight == kSlots) ? 0 : 1, ophase = 0;
#pragma unroll 1
            for (int i = kInflight; i < 2 * kNT; i++) {
                if (i == kInflight) TRACE2(4);
                mbar_wait(bar_full + oslot * 8, ophase);
                if (i == kInflight) TRACE2(5);
                if (i == kInflight + 1) TRACE2(6);
                if (++oslot == kSlots) { oslot = 0; ophase ^= 1; }
                if (i >= kSlots) mbar_wait(bar_empty + slot * 8, phase);
                mbar_expect_tx(bar_full + slot * 8, kSlotBytes);
                tma_load_2d(sbase + kOffRing + slot * kSlotBytes, (i & 1) ? &map_v : &map_k,
                            bar_full + slot * 8, 0, line0 + (i >> 1) * (2 * kTile));
                if (++slot == kSlots) { slot = 0; phase ^= 1; }
            }
        }
        __syncwarp();
        asm volatile("barrier.cluster.wait.acquire.aligned;" ::: "memory");
    } else {
        const int wg = warp >> 2;
        const int w = warp & 3;
        const int g = lane >> 2, j = lane & 3;
        const int m_row = w * 8 + g;
        const float kScale = 0.08838834764831845f;
        const float c = kScale * 1.4426950408889634f;

        uint32_t qf[4][4];
        {
            const uint32_t* r0 = reinterpret_cast<const uint32_t*>(q + ((size_t)group * kRows + m_row) * kD) + j;
#pragma unroll
            for (int kk = 0; kk < 4; kk++) {
                qf[kk][0] = __ldg(r0 + kk * 8);
                qf[kk][1] = __ldg(r0 + 32 + kk * 8);
                qf[kk][2] = __ldg(r0 + kk * 8 + 4);
                qf[kk][3] = __ldg(r0 + 32 + kk * 8 + 4);
            }
        }

        float o[32];
#pragma unroll
        for (int i = 0; i < 32; i++) o[i] = 0.f;
        float mrun = -INFINITY, lrun = 0.f;

        if (rank == 0 && wg == 1) {
            const int t128 = tid & 127;
            const int ln = t128 >> 3, ch = t128 & 7;
            const uint4 kv = __ldg(reinterpret_cast<const uint4*>(k_tree + (size_t)group * kT * kD) + t128);
            const uint4 vv = __ldg(reinterpret_cast<const uint4*>(v_tree + (size_t)group * kT * kD) + t128);
            const int b = group / kHkv;
            const float mk0 = __bfloat162float(tree_mask[b * kT * kT + g * kT + j]);
            const float mk1 = __bfloat162float(tree_mask[b * kT * kT + g * kT + 4 + j]);
            const uint32_t sw = (uint32_t)(ln * 128 + ((ch ^ (ln & 7)) * 16));
            asm volatile("st.shared.v4.b32 [%0], {%1,%2,%3,%4};" ::"r"(sbase + kOffKTree + sw), "r"(kv.x), "r"(kv.y), "r"(kv.z), "r"(kv.w) : "memory");
            asm volatile("st.shared.v4.b32 [%0], {%1,%2,%3,%4};" ::"r"(sbase + kOffVTree + sw), "r"(vv.x), "r"(vv.y), "r"(vv.z), "r"(vv.w) : "memory");
            asm volatile("fence.proxy.async.shared::cta;" ::: "memory");
            asm volatile("bar.sync 1, 128;" ::: "memory");

            float s[8];
            wgmma_fence();
#pragma unroll
            for (int kk = 0; kk < 4; kk++) {
                wgmma_n16(s, qf[kk], make_desc(sbase + kOffKTree + kk * 32), kk);
            }
            wgmma_commit();
            wgmma_wait<0>();
            const float madd = -1.0e9f / kScale;
            const float s0 = (s[0] + s[3]) + (1.f - mk0) * madd;
            const float s1 = (s[4] + s[7]) + (1.f - mk1) * madd;
            float mx = fmaxf(s0, s1);
            mx = fmaxf(mx, __shfl_xor_sync(0xffffffffu, mx, 1));
            mx = fmaxf(mx, __shfl_xor_sync(0xffffffffu, mx, 2));
            mrun = mx;
            const float p0 = ex2((s0 - mx) * c), p1 = ex2((s1 - mx) * c);
            lrun = p0 + p1;
            const uint32_t t = pack_bf16(p0, p1);
            uint32_t pa[4] = {t & 0xFFFFu, t << 16, t >> 16, t & 0xFFFF0000u};
            asm volatile("" : "+r"(pa[0]), "+r"(pa[1]), "+r"(pa[2]), "+r"(pa[3]));
            wgmma_fence();
            wgmma_pv(o, pa[0], pa[1], pa[2], pa[3], make_desc(sbase + kOffVTree));
            wgmma_commit();
            wgmma_wait<0>();
        }

        asm volatile("bar.sync 2, 288;" ::: "memory");
        asm volatile("barrier.cluster.arrive.relaxed.aligned;" ::: "memory");

        int slot = 2 * wg;
        uint32_t phase = 0;
#pragma unroll 1
        for (int it = 0; it < kNT / 2; it++) {
            float s[64];
            {
                const uint32_t kb = sbase + kOffRing + slot * kSlotBytes;
                mbar_wait(bar_full + slot * 8, phase);
                if (it == 0 && warp == 0) TRACE(1);
                if (it == kNT / 2 - 1 && warp == 4) TRACE(2);
                wgmma_fence();
#pragma unroll
                for (int kk = 0; kk < 4; kk++) {
                    wgmma_qk(s, qf[kk], make_desc(kb + kk * 32), kk);
                }
                wgmma_commit();
                wgmma_wait<0>();
                if (lane == 0) mbar_arrive(bar_empty + slot * 8);
            }
            float sv[16];
#pragma unroll
            for (int i = 0; i < 16; i++) sv[i] = s[4 * i] + s[4 * i + 3];
            float mx = fmaxf(sv[0], sv[1]);
#pragma unroll
            for (int i = 2; i < 16; i += 2) mx = fmaxf(mx, fmaxf(sv[i], sv[i + 1]));
            mx = fmaxf(mx, __shfl_xor_sync(0xffffffffu, mx, 1));
            mx = fmaxf(mx, __shfl_xor_sync(0xffffffffu, mx, 2));
            const float mn = fmaxf(mrun, mx);
            const float alpha = ex2((mrun - mn) * c);
            mrun = mn;
            const float mc = mn * c;
            float rs = 0.f;
            uint32_t pa[8][4];
#pragma unroll
            for (int u = 0; u < 8; u++) {
                const float p0 = ex2(fmaf(sv[2 * u], c, -mc));
                const float p1 = ex2(fmaf(sv[2 * u + 1], c, -mc));
                rs += p0 + p1;
                const uint32_t t = pack_bf16(p0, p1);
                pa[u][0] = t & 0xFFFFu; pa[u][1] = t << 16; pa[u][2] = t >> 16; pa[u][3] = t & 0xFFFF0000u;
                asm volatile("" : "+r"(pa[u][0]), "+r"(pa[u][1]), "+r"(pa[u][2]), "+r"(pa[u][3]));
            }
            lrun = lrun * alpha + rs;
#pragma unroll
            for (int i = 0; i < 32; i++) o[i] *= alpha;
            {
                const uint32_t vb = sbase + kOffRing + (slot + 1) * kSlotBytes;
                mbar_wait(bar_full + (slot + 1) * 8, phase);
                if (it == kNT / 2 - 1 && warp == 4) TRACE(3);
                wgmma_fence();
#pragma unroll
                for (int u = 0; u < 8; u++) {
                    wgmma_pv(o, pa[u][0], pa[u][1], pa[u][2], pa[u][3], make_desc(vb + u * 2048));
                }
                wgmma_commit();
                wgmma_wait<0>();
                if (lane == 0) mbar_arrive(bar_empty + (slot + 1) * 8);
            }
            slot += 4;
            if (slot >= kSlots) { slot -= kSlots; phase ^= 1; }
        }

        lrun += __shfl_xor_sync(0xffffffffu, lrun, 1);
        lrun += __shfl_xor_sync(0xffffffffu, lrun, 2);

        if (warp == 4) TRACE(4);
        asm volatile("barrier.cluster.wait.acquire.aligned;" ::: "memory");

        const int combo = rank * 2 + wg;
        if (combo != w) {
            const int src = combo < w ? combo : combo - 1;
            const uint32_t lbuf = sbase + kOffXbuf + ((w & 1) * 3 + src) * kXPart + lane * 16;
            uint32_t rbuf, rbar;
            asm volatile("mapa.shared::cluster.u32 %0, %1, %2;" : "=r"(rbuf) : "r"(lbuf), "r"(w >> 1));
            asm volatile("mapa.shared::cluster.u32 %0, %1, %2;" : "=r"(rbar) : "r"(bar_x + (w & 1) * 8), "r"(w >> 1));
#pragma unroll
            for (int i = 0; i < 8; i++) {
                asm volatile(
                    "st.async.weak.shared::cluster.mbarrier::complete_tx::bytes.v4.f32 [%0], {%1,%2,%3,%4}, [%5];"
                    ::"r"(rbuf + i * 512), "f"(o[4 * i]), "f"(o[4 * i + 1]), "f"(o[4 * i + 2]), "f"(o[4 * i + 3]), "r"(rbar)
                    : "memory");
            }
            asm volatile(
                "st.async.weak.shared::cluster.mbarrier::complete_tx::bytes.v4.f32 [%0], {%1,%2,%3,%4}, [%5];"
                ::"r"(rbuf + 8 * 512), "f"(mrun), "f"(lrun), "f"(0.f), "f"(0.f), "r"(rbar)
                : "memory");
        } else {
            mbar_wait(bar_x + (w & 1) * 8, 0);
            if (wg == 0) TRACE(5);
            const uint32_t lbuf = sbase + kOffXbuf + (w & 1) * 3 * kXPart + lane * 16;
            float pm[3], pl[3];
#pragma unroll
            for (int s2 = 0; s2 < 3; s2++) {
                asm volatile("ld.shared.v2.f32 {%0,%1}, [%2];" : "=f"(pm[s2]), "=f"(pl[s2]) : "r"(lbuf + s2 * kXPart + 8 * 512) : "memory");
            }
            const float mn = fmaxf(fmaxf(mrun, pm[0]), fmaxf(pm[1], pm[2]));
            float wa = ex2((mrun - mn) * c);
            float wb[3];
            float lsum = lrun * wa;
#pragma unroll
            for (int s2 = 0; s2 < 3; s2++) { wb[s2] = ex2((pm[s2] - mn) * c); lsum += pl[s2] * wb[s2]; }
            float inv;
            asm("rcp.approx.ftz.f32 %0, %1;" : "=f"(inv) : "f"(lsum));
            wa *= inv;
#pragma unroll
            for (int s2 = 0; s2 < 3; s2++) wb[s2] *= inv;
            uint32_t* w0 = reinterpret_cast<uint32_t*>(out + ((size_t)group * kRows + m_row) * kD) + j;
#pragma unroll
            for (int i = 0; i < 8; i++) {
                float r0 = o[4 * i] * wa, r1 = o[4 * i + 1] * wa, r2 = o[4 * i + 2] * wa, r3 = o[4 * i + 3] * wa;
#pragma unroll
                for (int s2 = 0; s2 < 3; s2++) {
                    float x0, x1, x2, x3;
                    asm volatile("ld.shared.v4.f32 {%0,%1,%2,%3}, [%4];" : "=f"(x0), "=f"(x1), "=f"(x2), "=f"(x3) : "r"(lbuf + s2 * kXPart + i * 512) : "memory");
                    r0 += x0 * wb[s2]; r1 += x1 * wb[s2]; r2 += x2 * wb[s2]; r3 += x3 * wb[s2];
                }
                w0[i * 4] = pack_bf16(r0, r1);
                w0[32 + i * 4] = pack_bf16(r2, r3);
            }
            if (wg == 0) TRACE(6);
        }
    }
}

typedef CUresult (*EncodeTiledFn)(CUtensorMap*, CUtensorMapDataType, cuuint32_t, void*, const cuuint64_t*,
                                  const cuuint64_t*, const cuuint32_t*, const cuuint32_t*,
                                  CUtensorMapInterleave, CUtensorMapSwizzle, CUtensorMapL2promotion,
                                  CUtensorMapFloatOOBfill);

static EncodeTiledFn get_encode_fn() {
    static EncodeTiledFn fn = nullptr;
    if (!fn) {
        void* p = nullptr;
        cudaDriverEntryPointQueryResult st;
        cudaGetDriverEntryPoint("cuTensorMapEncodeTiled", &p, cudaEnableDefault, &st);
        fn = reinterpret_cast<EncodeTiledFn>(p);
    }
    return fn;
}

#define TSV_L2PROMO CU_TENSOR_MAP_L2_PROMOTION_L2_256B

static void make_map(CUtensorMap* map, const void* ptr) {
    cuuint64_t gdim[2] = {64, (cuuint64_t)kB * kHkv * kC * 2};
    cuuint64_t gstride[1] = {128};
    cuuint32_t box[2] = {64, (cuuint32_t)(2 * kTile)};
    cuuint32_t estr[2] = {1, 1};
    get_encode_fn()(map, CU_TENSOR_MAP_DATA_TYPE_BFLOAT16, 2, const_cast<void*>(ptr), gdim, gstride, box, estr,
                    CU_TENSOR_MAP_INTERLEAVE_NONE, CU_TENSOR_MAP_SWIZZLE_128B, TSV_L2PROMO,
                    CU_TENSOR_MAP_FLOAT_OOB_FILL_NONE);
}

}

extern "C" void kernel_launch(void* const* d_in, const int* in_sizes, int n_in,
                              void* d_out, int out_size) {
    using namespace tsv;
    const __nv_bfloat16* q = (const __nv_bfloat16*)d_in[0];
    const __nv_bfloat16* k_cache = (const __nv_bfloat16*)d_in[1];
    const __nv_bfloat16* v_cache = (const __nv_bfloat16*)d_in[2];
    const __nv_bfloat16* k_tree = (const __nv_bfloat16*)d_in[3];
    const __nv_bfloat16* v_tree = (const __nv_bfloat16*)d_in[4];
    const __nv_bfloat16* tree_mask = (const __nv_bfloat16*)d_in[5];
    __nv_bfloat16* out = (__nv_bfloat16*)d_out;

    CUtensorMap map_k, map_v;
    make_map(&map_k, k_cache);
    make_map(&map_v, v_cache);

    static bool attr_set = false;
    if (!attr_set) {
        cudaFuncSetAttribute(tree_attn_kernel, cudaFuncAttributeMaxDynamicSharedMemorySize, kSmemBytes);
        attr_set = true;
    }
    tree_attn_kernel<<<kB * kHkv * kSplit, kThreads, kSmemBytes>>>(map_k, map_v, q, k_tree, v_tree, tree_mask, out);
}
```

```cpp
#include <cuda_runtime.h>
#include <cuda_bf16.h>
#include <cuda.h>
#include <stdint.h>

namespace tsv {

constexpr int kB = 8, kHq = 32, kHkv = 8, kT = 8, kC = 4096, kD = 128;
constexpr int kRep = kHq / kHkv;
constexpr int kRows = kRep * kT;
constexpr int kSplit = 2;
constexpr int kCtas = kB * kHkv * kSplit;
constexpr int kKeysPerCta = kC / kSplit;
constexpr int kTile = 64;
constexpr int kNT = kKeysPerCta / kTile;
constexpr int kSlots = 8;
constexpr int kInflight = 4;
static_assert(kSlots % 4 == 0, "each ring slot must always belong to the same consumer warpgroup");
constexpr int kSlotBytes = kTile * kD * 2;
constexpr int kThreads = 288;

constexpr int kOffRing = 0;
constexpr int kOffKTree = kOffRing + kSlots * kSlotBytes;
constexpr int kOffVTree = kOffKTree + 2048;
constexpr int kOffXbuf = kOffVTree + 2048;
constexpr int kXPart = 9 * 32 * 16;
constexpr int kXbufBytes = 2 * 3 * kXPart;
constexpr int kOffBars = kOffXbuf + kXbufBytes;
constexpr int kSmemBytes = kOffBars + (2 * kSlots + 4) * 8 + 1024;

__device__ __forceinline__ uint32_t smem_u32(const void* p) {
    return (uint32_t)__cvta_generic_to_shared(p);
}
__device__ __forceinline__ void mbar_init(uint32_t bar, uint32_t count) {
    asm volatile("mbarrier.init.shared::cta.b64 [%0], %1;" ::"r"(bar), "r"(count) : "memory");
}
__device__ __forceinline__ void mbar_expect_tx(uint32_t bar, uint32_t bytes) {
    asm volatile("mbarrier.arrive.expect_tx.shared::cta.b64 _, [%0], %1;" ::"r"(bar), "r"(bytes) : "memory");
}
__device__ __forceinline__ void mbar_arrive(uint32_t bar) {
    asm volatile("mbarrier.arrive.shared::cta.b64 _, [%0];" ::"r"(bar) : "memory");
}
__device__ __forceinline__ bool mbar_try_wait(uint32_t bar, uint32_t parity) {
    uint32_t ok;
    asm volatile(
        "{\n.reg .pred p;\n"
        "mbarrier.try_wait.parity.shared::cta.b64 p, [%1], %2;\n"
        "selp.u32 %0, 1, 0, p;\n}\n"
        : "=r"(ok) : "r"(bar), "r"(parity) : "memory");
    return ok != 0;
}
__device__ __forceinline__ void mbar_wait(uint32_t bar, uint32_t parity) {
    uint32_t spins = 0;
    while (!mbar_try_wait(bar, parity)) {
        if (++spins > (1u << 20)) __trap();
    }
}
__device__ __forceinline__ void tma_load_2d(uint32_t dst, const CUtensorMap* map, uint32_t bar,
                                            int c0, int c1) {
    asm volatile(
        "cp.async.bulk.tensor.2d.shared::cluster.global.mbarrier::complete_tx::bytes "
        "[%0], [%1, {%3, %4}], [%2];"
        ::"r"(dst), "l"(reinterpret_cast<uint64_t>(map)), "r"(bar), "r"(c0), "r"(c1)
        : "memory");
}
__device__ __forceinline__ void wgmma_fence() { asm volatile("wgmma.fence.sync.aligned;" ::: "memory"); }
__device__ __forceinline__ void wgmma_commit() { asm volatile("wgmma.commit_group.sync.aligned;" ::: "memory"); }
template <int N>
__device__ __forceinline__ void wgmma_wait() {
    asm volatile("wgmma.wait_group.sync.aligned %0;" ::"n"(N) : "memory");
}
__device__ __forceinline__ uint64_t make_desc(uint32_t addr) {
    return (uint64_t)((addr & 0x3FFFF) >> 4) | (1ull << 16) | (64ull << 32) | (1ull << 62);
}
__device__ __forceinline__ float ex2(float x) {
    float y;
    asm("ex2.approx.ftz.f32 %0, %1;" : "=f"(y) : "f"(x));
    return y;
}
__device__ __forceinline__ uint32_t pack_bf16(float lo, float hi) {
    uint32_t r;
    asm("cvt.rn.bf16x2.f32 %0, %1, %2;" : "=r"(r) : "f"(hi), "f"(lo));
    return r;
}
__device__ __forceinline__ uint32_t now_ns() {
    uint32_t t;
    asm volatile("mov.u32 %0, %globaltimer_lo;" : "=r"(t));
    return t;
}

#define TSV_F8(d, o) "+f"(d[o + 0]), "+f"(d[o + 1]), "+f"(d[o + 2]), "+f"(d[o + 3]), \
                     "+f"(d[o + 4]), "+f"(d[o + 5]), "+f"(d[o + 6]), "+f"(d[o + 7])

__device__ __forceinline__ void wgmma_n16(float (&d)[8], const uint32_t (&a)[4], uint64_t desc, int scale_d) {
    asm volatile(
        "{\n.reg .pred p;\nsetp.ne.b32 p, %13, 0;\n"
        "wgmma.mma_async.sync.aligned.m64n16k16.f32.bf16.bf16 "
        "{%0,%1,%2,%3,%4,%5,%6,%7}, {%8,%9,%10,%11}, %12, p, 1, 1, 0;\n}\n"
        : TSV_F8(d, 0)
        : "r"(a[0]), "r"(a[1]), "r"(a[2]), "r"(a[3]), "l"(desc), "r"(scale_d));
}

__device__ __forceinline__ void wgmma_pv(float (&d)[32], uint32_t a0, uint32_t a1, uint32_t a2, uint32_t a3,
                                         uint64_t desc) {
    asm volatile(
        "wgmma.mma_async.sync.aligned.m64n64k16.f32.bf16.bf16 "
        "{%0,%1,%2,%3,%4,%5,%6,%7,%8,%9,%10,%11,%12,%13,%14,%15,"
        "%16,%17,%18,%19,%20,%21,%22,%23,%24,%25,%26,%27,%28,%29,%30,%31}, "
        "{%32,%33,%34,%35}, %36, 1, 1, 1, 1;\n"
        : TSV_F8(d, 0), TSV_F8(d, 8), TSV_F8(d, 16), TSV_F8(d, 24)
        : "r"(a0), "r"(a1), "r"(a2), "r"(a3), "l"(desc));
}

__device__ __forceinline__ void wgmma_qk(float (&d)[64], const uint32_t (&a)[4], uint64_t desc, int scale_d) {
    asm volatile(
        "{\n.reg .pred p;\nsetp.ne.b32 p, %69, 0;\n"
        "wgmma.mma_async.sync.aligned.m64n128k16.f32.bf16.bf16 "
        "{%0,%1,%2,%3,%4,%5,%6,%7,%8,%9,%10,%11,%12,%13,%14,%15,"
        "%16,%17,%18,%19,%20,%21,%22,%23,%24,%25,%26,%27,%28,%29,%30,%31,"
        "%32,%33,%34,%35,%36,%37,%38,%39,%40,%41,%42,%43,%44,%45,%46,%47,"
        "%48,%49,%50,%51,%52,%53,%54,%55,%56,%57,%58,%59,%60,%61,%62,%63}, "
        "{%64,%65,%66,%67}, %68, p, 1, 1, 0;\n}\n"
        : TSV_F8(d, 0), TSV_F8(d, 8), TSV_F8(d, 16), TSV_F8(d, 24),
          TSV_F8(d, 32), TSV_F8(d, 40), TSV_F8(d, 48), TSV_F8(d, 56)
        : "r"(a[0]), "r"(a[1]), "r"(a[2]), "r"(a[3]), "l"(desc), "r"(scale_d));
}

constexpr int kLastPos = 2 * kNT - 1;
__device__ __forceinline__ uint32_t pos_bar(uint32_t bar_full, uint32_t bar_s, int p) {
    return p == 0 ? bar_s : (p == kLastPos ? bar_s + 8 : bar_full + (p % kSlots) * 8);
}
__device__ __forceinline__ uint32_t pos_parity(int p) {
    return (p == 0 || p == kLastPos) ? 0u : (uint32_t)((p / kSlots) - (p % kSlots == 0 ? 1 : 0)) & 1u;
}
__device__ __forceinline__ void issue_pos(int p, uint32_t sbase, uint32_t bar_full, uint32_t bar_s,
                                          const CUtensorMap* map_k, const CUtensorMap* map_v, int line0) {
    const bool is_v = p == kLastPos || (p != 0 && (p & 1) == 0);
    const int tile = p == kLastPos ? kNT - 1 : (is_v ? (p >> 1) - 1 : (p + 1) >> 1);
    const uint32_t fb = pos_bar(bar_full, bar_s, p);
    mbar_expect_tx(fb, kSlotBytes);
    tma_load_2d(sbase + kOffRing + (p % kSlots) * kSlotBytes, is_v ? map_v : map_k, fb, 0,
                line0 + tile * (2 * kTile));
}

__global__ void __cluster_dims__(kSplit, 1, 1) __launch_bounds__(kThreads, 1)
tree_attn_kernel(const __grid_constant__ CUtensorMap map_k,
                 const __grid_constant__ CUtensorMap map_v,
                 const __nv_bfloat16* __restrict__ q,
                 const __nv_bfloat16* __restrict__ k_tree,
                 const __nv_bfloat16* __restrict__ v_tree,
                 const __nv_bfloat16* __restrict__ tree_mask,
                 __nv_bfloat16* __restrict__ out,
                 uint32_t pace_ns, uint32_t pace_off_ns) {
    extern __shared__ uint8_t smem_raw[];
    const uint32_t sbase = (smem_u32(smem_raw) + 1023u) & ~1023u;
    const uint32_t bar_full = sbase + kOffBars;
    const uint32_t bar_empty = bar_full + kSlots * 8;
    const uint32_t bar_x = bar_empty + kSlots * 8;
    const uint32_t bar_s = bar_x + 16;

    const int tid = threadIdx.x;
    const int warp = tid >> 5;
    const int lane = tid & 31;
    const int group = blockIdx.x >> 1;
    const int rank = blockIdx.x & 1;
    const int line0 = 2 * (group * kC + rank * kKeysPerCta);

    if (tid == 256) {
        asm volatile("prefetch.tensormap [%0];" ::"l"(reinterpret_cast<uint64_t>(&map_k)) : "memory");
        asm volatile("prefetch.tensormap [%0];" ::"l"(reinterpret_cast<uint64_t>(&map_v)) : "memory");
        mbar_init(bar_s, 1);
#pragma unroll
        for (int i = 1; i < kInflight; i++) mbar_init(bar_full + i * 8, 1);
#pragma unroll 1
        for (int i = 0; i < kInflight; i++) {
            issue_pos(i, sbase, bar_full, bar_s, &map_k, &map_v, line0);
        }
#pragma unroll 1
        for (int i = 0; i < kSlots; i++) {
            if (i >= kInflight || i == 0) mbar_init(bar_full + i * 8, 1);
            mbar_init(bar_empty + i * 8, 4);
        }
        mbar_init(bar_s + 8, 1);
        mbar_init(bar_x, 1);
        mbar_init(bar_x + 8, 1);
        asm volatile("fence.mbarrier_init.release.cluster;" ::: "memory");
        mbar_expect_tx(bar_x, 3 * kXPart);
        mbar_expect_tx(bar_x + 8, 3 * kXPart);
    }
    if (warp == 8) {
        __syncwarp();
        asm volatile("bar.arrive 2, 288;" ::: "memory");
        asm volatile("barrier.cluster.arrive.relaxed.aligned;" ::: "memory");
        if (lane == 0) {
            uint32_t t_next = now_ns() + pace_off_ns;
#pragma unroll 1
            for (int i = kInflight; i <= kLastPos; i++) {
                mbar_wait(pos_bar(bar_full, bar_s, i - kInflight), pos_parity(i - kInflight));
                if (i >= kSlots) mbar_wait(bar_empty + (i % kSlots) * 8, ((i / kSlots) - 1) & 1);
                for (int spin = 0; spin < (1 << 16) && (int)(now_ns() - t_next) < 0; spin++) { }
                t_next += pace_ns;
                issue_pos(i, sbase, bar_full, bar_s, &map_k, &map_v, line0);
            }
        }
        __syncwarp();
        asm volatile("barrier.cluster.wait.acquire.aligned;" ::: "memory");
    } else {
        const int wg = warp >> 2;
        const int w = warp & 3;
        const int g = lane >> 2, j = lane & 3;
        const int m_row = w * 8 + g;
        const float kScale = 0.08838834764831845f;
        const float c = kScale * 1.4426950408889634f;

        uint32_t qf[4][4];
        {
            const uint32_t* r0 = reinterpret_cast<const uint32_t*>(q + ((size_t)group * kRows + m_row) * kD) + j;
#pragma unroll
            for (int kk = 0; kk < 4; kk++) {
                qf[kk][0] = __ldg(r0 + kk * 8);
                qf[kk][1] = __ldg(r0 + 32 + kk * 8);
                qf[kk][2] = __ldg(r0 + kk * 8 + 4);
                qf[kk][3] = __ldg(r0 + 32 + kk * 8 + 4);
            }
        }

        float o[32];
#pragma unroll
        for (int i = 0; i < 32; i++) o[i] = 0.f;
        float mrun = -INFINITY, lrun = 0.f;

        if (rank == 0 && wg == 1) {
            const int t128 = tid & 127;
            const int ln = t128 >> 3, ch = t128 & 7;
            const uint4 kv = __ldg(reinterpret_cast<const uint4*>(k_tree + (size_t)group * kT * kD) + t128);
            const uint4 vv = __ldg(reinterpret_cast<const uint4*>(v_tree + (size_t)group * kT * kD) + t128);
            const int b = group / kHkv;
            const float mk0 = __bfloat162float(tree_mask[b * kT * kT + g * kT + j]);
            const float mk1 = __bfloat162float(tree_mask[b * kT * kT + g * kT + 4 + j]);
            const uint32_t sw = (uint32_t)(ln * 128 + ((ch ^ (ln & 7)) * 16));
            asm volatile("st.shared.v4.b32 [%0], {%1,%2,%3,%4};" ::"r"(sbase + kOffKTree + sw), "r"(kv.x), "r"(kv.y), "r"(kv.z), "r"(kv.w) : "memory");
            asm volatile("st.shared.v4.b32 [%0], {%1,%2,%3,%4};" ::"r"(sbase + kOffVTree + sw), "r"(vv.x), "r"(vv.y), "r"(vv.z), "r"(vv.w) : "memory");
            asm volatile("fence.proxy.async.shared::cta;" ::: "memory");
            asm volatile("bar.sync 1, 128;" ::: "memory");

            float s[8];
            wgmma_fence();
#pragma unroll
            for (int kk = 0; kk < 4; kk++) {
                wgmma_n16(s, qf[kk], make_desc(sbase + kOffKTree + kk * 32), kk);
            }
            wgmma_commit();
            wgmma_wait<0>();
            const float madd = -1.0e9f / kScale;
            const float s0 = (s[0] + s[3]) + (1.f - mk0) * madd;
            const float s1 = (s[4] + s[7]) + (1.f - mk1) * madd;
            float mx = fmaxf(s0, s1);
            mx = fmaxf(mx, __shfl_xor_sync(0xffffffffu, mx, 1));
            mx = fmaxf(mx, __shfl_xor_sync(0xffffffffu, mx, 2));
            mrun = mx;
            const float p0 = ex2((s0 - mx) * c), p1 = ex2((s1 - mx) * c);
            lrun = p0 + p1;
            const uint32_t t = pack_bf16(p0, p1);
            uint32_t pa[4] = {t & 0xFFFFu, t << 16, t >> 16, t & 0xFFFF0000u};
            asm volatile("" : "+r"(pa[0]), "+r"(pa[1]), "+r"(pa[2]), "+r"(pa[3]));
            wgmma_fence();
            wgmma_pv(o, pa[0], pa[1], pa[2], pa[3], make_desc(sbase + kOffVTree));
            wgmma_commit();
            wgmma_wait<0>();
        }

        asm volatile("bar.sync 2, 288;" ::: "memory");
        asm volatile("barrier.cluster.arrive.relaxed.aligned;" ::: "memory");

        const int combo = rank * 2 + wg;
        uint32_t xbuf, xbar;
        if (combo != w) {
            const int src = combo < w ? combo : combo - 1;
            const uint32_t lbuf = sbase + kOffXbuf + ((w & 1) * 3 + src) * kXPart + lane * 16;
            asm volatile("mapa.shared::cluster.u32 %0, %1, %2;" : "=r"(xbuf) : "r"(lbuf), "r"(w >> 1));
            asm volatile("mapa.shared::cluster.u32 %0, %1, %2;" : "=r"(xbar) : "r"(bar_x + (w & 1) * 8), "r"(w >> 1));
        } else {
            xbuf = sbase + kOffXbuf + (w & 1) * 3 * kXPart + lane * 16;
            xbar = bar_x + (w & 1) * 8;
        }
        asm volatile("barrier.cluster.wait.acquire.aligned;" ::: "memory");

#pragma unroll 1
        for (int it = 0; it < kNT / 2; it++) {
            const int t = 2 * it + wg;
            const int pk = t == 0 ? 0 : 2 * t - 1;
            const int pv = t == kNT - 1 ? kLastPos : 2 * t + 2;
            float s[64];
            {
                const uint32_t kb = sbase + kOffRing + (pk % kSlots) * kSlotBytes;
                mbar_wait(pos_bar(bar_full, bar_s, pk), pos_parity(pk));
                wgmma_fence();
#pragma unroll
                for (int kk = 0; kk < 4; kk++) {
                    wgmma_qk(s, qf[kk], make_desc(kb + kk * 32), kk);
                }
                wgmma_commit();
                wgmma_wait<0>();
                if (lane == 0) mbar_arrive(bar_empty + (pk % kSlots) * 8);
            }
            float sv[16];
#pragma unroll
            for (int i = 0; i < 16; i++) sv[i] = s[4 * i] + s[4 * i + 3];
            float mx = fmaxf(sv[0], sv[1]);
#pragma unroll
            for (int i = 2; i < 16; i += 2) mx = fmaxf(mx, fmaxf(sv[i], sv[i + 1]));
            mx = fmaxf(mx, __shfl_xor_sync(0xffffffffu, mx, 1));
            mx = fmaxf(mx, __shfl_xor_sync(0xffffffffu, mx, 2));
            const float mn = fmaxf(mrun, mx);
            const float alpha = ex2((mrun - mn) * c);
            mrun = mn;
            const float mc = mn * c;
            float rs = 0.f;
            uint32_t pa[8][4];
#pragma unroll
            for (int u = 0; u < 8; u++) {
                const float p0 = ex2(fmaf(sv[2 * u], c, -mc));
                const float p1 = ex2(fmaf(sv[2 * u + 1], c, -mc));
                rs += p0 + p1;
                const uint32_t tt = pack_bf16(p0, p1);
                pa[u][0] = tt & 0xFFFFu; pa[u][1] = tt << 16; pa[u][2] = tt >> 16; pa[u][3] = tt & 0xFFFF0000u;
                asm volatile("" : "+r"(pa[u][0]), "+r"(pa[u][1]), "+r"(pa[u][2]), "+r"(pa[u][3]));
            }
            lrun = lrun * alpha + rs;
#pragma unroll
            for (int i = 0; i < 32; i++) o[i] *= alpha;
            {
                const uint32_t vb = sbase + kOffRing + (pv % kSlots) * kSlotBytes;
                mbar_wait(pos_bar(bar_full, bar_s, pv), pos_parity(pv));
                wgmma_fence();
#pragma unroll
                for (int u = 0; u < 8; u++) {
                    wgmma_pv(o, pa[u][0], pa[u][1], pa[u][2], pa[u][3], make_desc(vb + u * 2048));
                }
                wgmma_commit();
                wgmma_wait<0>();
                if (lane == 0) mbar_arrive(bar_empty + (pv % kSlots) * 8);
            }
        }

        if (combo != w) {
#pragma unroll
            for (int i = 0; i < 8; i++) {
                asm volatile(
                    "st.async.weak.shared::cluster.mbarrier::complete_tx::bytes.v4.f32 [%0], {%1,%2,%3,%4}, [%5];"
                    ::"r"(xbuf + i * 512), "f"(o[4 * i]), "f"(o[4 * i + 1]), "f"(o[4 * i + 2]), "f"(o[4 * i + 3]), "r"(xbar)
                    : "memory");
            }
            asm volatile(
                "st.async.weak.shared::cluster.mbarrier::complete_tx::bytes.v4.f32 [%0], {%1,%2,%3,%4}, [%5];"
                ::"r"(xbuf + 8 * 512), "f"(mrun), "f"(lrun), "f"(0.f), "f"(0.f), "r"(xbar)
                : "memory");
        } else {
            mbar_wait(xbar, 0);
            float pm[3], pl[3];
#pragma unroll
            for (int s2 = 0; s2 < 3; s2++) {
                asm volatile("ld.shared.v2.f32 {%0,%1}, [%2];" : "=f"(pm[s2]), "=f"(pl[s2]) : "r"(xbuf + s2 * kXPart + 8 * 512) : "memory");
            }
            const float mn = fmaxf(fmaxf(mrun, pm[0]), fmaxf(pm[1], pm[2]));
            float wa = ex2((mrun - mn) * c);
            float wb[3];
            float lsum = lrun * wa;
#pragma unroll
            for (int s2 = 0; s2 < 3; s2++) { wb[s2] = ex2((pm[s2] - mn) * c); lsum += pl[s2] * wb[s2]; }
            lsum += __shfl_xor_sync(0xffffffffu, lsum, 1);
            lsum += __shfl_xor_sync(0xffffffffu, lsum, 2);
            float inv;
            asm("rcp.approx.ftz.f32 %0, %1;" : "=f"(inv) : "f"(lsum));
            wa *= inv;
#pragma unroll
            for (int s2 = 0; s2 < 3; s2++) wb[s2] *= inv;
            uint32_t* w0 = reinterpret_cast<uint32_t*>(out + ((size_t)group * kRows + m_row) * kD) + j;
#pragma unroll
            for (int i = 0; i < 8; i++) {
                float r0 = o[4 * i] * wa, r1 = o[4 * i + 1] * wa, r2 = o[4 * i + 2] * wa, r3 = o[4 * i + 3] * wa;
#pragma unroll
                for (int s2 = 0; s2 < 3; s2++) {
                    float x0, x1, x2, x3;
                    asm volatile("ld.shared.v4.f32 {%0,%1,%2,%3}, [%4];" : "=f"(x0), "=f"(x1), "=f"(x2), "=f"(x3) : "r"(xbuf + s2 * kXPart + i * 512) : "memory");
                    r0 += x0 * wb[s2]; r1 += x1 * wb[s2]; r2 += x2 * wb[s2]; r3 += x3 * wb[s2];
                }
                w0[i * 4] = pack_bf16(r0, r1);
                w0[32 + i * 4] = pack_bf16(r2, r3);
            }
        }
    }
}

typedef CUresult (*EncodeTiledFn)(CUtensorMap*, CUtensorMapDataType, cuuint32_t, void*, const cuuint64_t*,
                                  const cuuint64_t*, const cuuint32_t*, const cuuint32_t*,
                                  CUtensorMapInterleave, CUtensorMapSwizzle, CUtensorMapL2promotion,
                                  CUtensorMapFloatOOBfill);

static EncodeTiledFn get_encode_fn() {
    static EncodeTiledFn fn = nullptr;
    if (!fn) {
        void* p = nullptr;
        cudaDriverEntryPointQueryResult st;
        cudaGetDriverEntryPoint("cuTensorMapEncodeTiled", &p, cudaEnableDefault, &st);
        fn = reinterpret_cast<EncodeTiledFn>(p);
    }
    return fn;
}

static void make_map(CUtensorMap* map, const void* ptr) {
    cuuint64_t gdim[2] = {64, (cuuint64_t)kB * kHkv * kC * 2};
    cuuint64_t gstride[1] = {128};
    cuuint32_t box[2] = {64, (cuuint32_t)(2 * kTile)};
    cuuint32_t estr[2] = {1, 1};
    get_encode_fn()(map, CU_TENSOR_MAP_DATA_TYPE_BFLOAT16, 2, const_cast<void*>(ptr), gdim, gstride, box, estr,
                    CU_TENSOR_MAP_INTERLEAVE_NONE, CU_TENSOR_MAP_SWIZZLE_128B, CU_TENSOR_MAP_L2_PROMOTION_L2_256B,
                    CU_TENSOR_MAP_FLOAT_OOB_FILL_NONE);
}

}

#define TSV_ETA 0.94
#define TSV_TOFF 600

extern "C" void kernel_launch(void* const* d_in, const int* in_sizes, int n_in,
                              void* d_out, int out_size) {
    using namespace tsv;
    const __nv_bfloat16* q = (const __nv_bfloat16*)d_in[0];
    const __nv_bfloat16* k_cache = (const __nv_bfloat16*)d_in[1];
    const __nv_bfloat16* v_cache = (const __nv_bfloat16*)d_in[2];
    const __nv_bfloat16* k_tree = (const __nv_bfloat16*)d_in[3];
    const __nv_bfloat16* v_tree = (const __nv_bfloat16*)d_in[4];
    const __nv_bfloat16* tree_mask = (const __nv_bfloat16*)d_in[5];
    __nv_bfloat16* out = (__nv_bfloat16*)d_out;

    CUtensorMap map_k, map_v;
    make_map(&map_k, k_cache);
    make_map(&map_v, v_cache);

    static bool init_done = false;
    static uint32_t pace_ns = 0, pace_off_ns = 0;
    if (!init_done) {
        cudaFuncSetAttribute(tree_attn_kernel, cudaFuncAttributeMaxDynamicSharedMemorySize, kSmemBytes);
        int dev = 0, clk_khz = 0, bus_bits = 0;
        cudaGetDevice(&dev);
        cudaDeviceGetAttribute(&clk_khz, cudaDevAttrMemoryClockRate, dev);
        cudaDeviceGetAttribute(&bus_bits, cudaDevAttrGlobalMemoryBusWidth, dev);
        const double peak = 2.0 * (double)clk_khz * 1e3 * (double)bus_bits / 8.0;
        if (peak > 1e11) {
            pace_ns = (uint32_t)((double)kCtas * kSlotBytes / (TSV_ETA * peak) * 1e9 + 0.5);
            pace_off_ns = TSV_TOFF;
        }
        (void)cudaGetLastError();
        init_done = true;
    }
    tree_attn_kernel<<<kCtas, kThreads, kSmemBytes>>>(map_k, map_v, q, k_tree, v_tree, tree_mask, out,
                                                      pace_ns, pace_off_ns);
}
```
